```python
import torch

def _softmax(x, axis=-1):
    return torch.softmax(x, dim=axis)
def _gelu(x):
    return torch.nn.functional.gelu(x, approximate="tanh")
def _silu(x):
    return torch.nn.functional.silu(x)
def _sigmoid(x):
    return torch.sigmoid(x)
def _layernorm(x, axis=-1, eps=1e-5):
    m = x.mean(dim=axis, keepdim=True)
    v = x.var(dim=axis, keepdim=True, unbiased=False)
    return (x - m) / torch.sqrt(v + eps)
def _scatter_add(tgt, idx, src, axis=0):
    return tgt.clone().index_add_(axis, idx, src)
def _segment_sum(src, seg, n):
    out = torch.zeros((n,) + src.shape[1:], dtype=src.dtype)
    return out.index_add_(0, seg, src)
def _pad(x, pw):
    flat = tuple(v for pair in reversed(pw) for v in pair)
    return torch.nn.functional.pad(x, flat)

kernel_name = 'interleave_layers__ssm_conv_h3__glu_gated_glu__prompt'

def setup_inputs():

    _w = (lambda a: (lambda t: t.to(torch.bfloat16) if t.is_floating_point() else t)(torch.as_tensor(a)))
    def _A_setup():
        B, S, D = 1, 2048, 512
        ks = 4
        return {
            "q": _w((lambda *s: torch.randn(*s, dtype=torch.bfloat16) * 0.05)(B, S, D)),
            "k": _w((lambda *s: torch.randn(*s, dtype=torch.bfloat16) * 0.4)(B, S, D)),
            "v": _w((lambda *s: torch.randn(*s, dtype=torch.bfloat16) * 0.4)(B, S, D)),
            "shift_k": _w((lambda *s: torch.randn(*s, dtype=torch.bfloat16) * 0.4)(D, ks) * 0.5),
            "ssm_k": _w((lambda *s: torch.randn(*s, dtype=torch.bfloat16) * 0.4)(D, S) * (1.0 / S ** 0.5)),
            "ssm_D": _w((lambda *s: torch.randn(*s, dtype=torch.bfloat16) * 0.4)(D)),
        }
    _A_in = _A_setup()

    def _B_setup():
        B, S, D, F = 1, 2048, 512, 1792
        return {
            "x": _w((lambda *s: torch.randn(*s, dtype=torch.bfloat16) * 0.05)(B, S, D)),
            "w_gate": _w((lambda *s: torch.randn(*s, dtype=torch.bfloat16) * 0.05)(D, F)),
            "w_up": _w((lambda *s: torch.randn(*s, dtype=torch.bfloat16) * 0.05)(D, F)),
            "w_down": _w((lambda *s: torch.randn(*s, dtype=torch.bfloat16) * 0.05)(F, D)),
        }
    _B_in = _B_setup()

    return {
        "A_q": _A_in["q"],
        "A_k": _A_in["k"],
        "A_v": _A_in["v"],
        "A_shift_k": _A_in["shift_k"],
        "A_ssm_k": _A_in["ssm_k"],
        "A_ssm_D": _A_in["ssm_D"],
        "B_x": _B_in["x"],
        "B_w_gate": _B_in["w_gate"],
        "B_w_up": _B_in["w_up"],
        "B_w_down": _B_in["w_down"],
    }

def reference(A_q, A_k, A_v, A_shift_k, A_ssm_k, A_ssm_D, B_x, B_w_gate, B_w_up, B_w_down):
    def _A_ref(q, k, v, shift_k, ssm_k, ssm_D):
        B, S, D = q.shape
        ks = shift_k.shape[-1]
        k_pad = _pad(k, ((0, 0), (ks - 1, 0), (0, 0)))
        k_shift = torch.zeros_like(k)
        for t in range(ks):
            k_shift = k_shift + k_pad[:, t:t + S, :] * shift_k[:, ks - 1 - t][None, None, :]
        kv = k_shift * v
        L = 2 * S
        kv_pad = _pad(kv, ((0, 0), (0, S), (0, 0)))
        kf_pad = _pad(ssm_k, ((0, 0), (0, S)))
        kv_f = (lambda x, axes=(-2,-1): torch.fft.rfft2(x.float(), dim=axes))(kv_pad[:, None, :, :], axes=(1, 2))
        kf_f = (lambda x, axes=(-2,-1): torch.fft.rfft2(x.float(), dim=axes))(kf_pad[:, None, :], axes=(1, 2))
        kf_f = (lambda x, *d: x.permute(*d))(kf_f, 1, 2, 0)
        y_f = kv_f * kf_f[None, :, :, :]
        y = (lambda x, s, axes=(-2,-1): torch.fft.irfft2(x, s=s, dim=axes).to(torch.bfloat16))(y_f, (1, L), axes=(1, 2))[:, 0, :S, :]
        y = y + kv * ssm_D[None, None, :]
        return q * y

    def _B_ref(x, w_gate, w_up, w_down):
        g = torch.einsum("bsd,df->bsf", x, w_gate)
        u = torch.einsum("bsd,df->bsf", x, w_up)
        h = _sigmoid(g) * u
        return torch.einsum("bsf,fd->bsd", h, w_down)

    x = A_q
    x = x + _A_ref(_layernorm(x, axis=-1), A_k, A_v, A_shift_k, A_ssm_k, A_ssm_D)
    x = x + _B_ref(_layernorm(x, axis=-1), B_w_gate, B_w_up, B_w_down)
    x = x + _A_ref(_layernorm(x, axis=-1), A_k, A_v, A_shift_k, A_ssm_k, A_ssm_D)
    x = x + _B_ref(_layernorm(x, axis=-1), B_w_gate, B_w_up, B_w_down)
    return x
```

```cpp
#include <cuda_runtime.h>
#include <cuda_bf16.h>
#include <cuda.h>
#include <stdint.h>

template<int N, int TB> struct WgRS;
template<int N, int TB> struct WgSS;
template<> struct WgRS<32,0> { template<int OB, unsigned HB, int SD> static __device__ __forceinline__ void run(float* d, uint32_t a0, uint32_t a1, uint32_t a2, uint32_t a3, uint32_t lb) {
  asm volatile("{.reg .pred p; .reg .b32 t; .reg .b64 db; add.s32 t,%20,%21; mov.b64 db,{t,%22}; setp.ne.b32 p,%23,0; wgmma.mma_async.sync.aligned.m64n32k16.f32.bf16.bf16 {%0,%1,%2,%3,%4,%5,%6,%7,%8,%9,%10,%11,%12,%13,%14,%15},{%16,%17,%18,%19},db,p,1,1,0;}"
    : "+f"(d[0]),"+f"(d[1]),"+f"(d[2]),"+f"(d[3]),"+f"(d[4]),"+f"(d[5]),"+f"(d[6]),"+f"(d[7]),"+f"(d[8]),"+f"(d[9]),"+f"(d[10]),"+f"(d[11]),"+f"(d[12]),"+f"(d[13]),"+f"(d[14]),"+f"(d[15])
    : "r"(a0),"r"(a1),"r"(a2),"r"(a3),"r"(lb),"n"(OB),"n"(HB),"n"(SD));
} };
template<> struct WgRS<64,0> { template<int OB, unsigned HB, int SD> static __device__ __forceinline__ void run(float* d, uint32_t a0, uint32_t a1, uint32_t a2, uint32_t a3, uint32_t lb) {
  asm volatile("{.reg .pred p; .reg .b32 t; .reg .b64 db; add.s32 t,%36,%37; mov.b64 db,{t,%38}; setp.ne.b32 p,%39,0; wgmma.mma_async.sync.aligned.m64n64k16.f32.bf16.bf16 {%0,%1,%2,%3,%4,%5,%6,%7,%8,%9,%10,%11,%12,%13,%14,%15,%16,%17,%18,%19,%20,%21,%22,%23,%24,%25,%26,%27,%28,%29,%30,%31},{%32,%33,%34,%35},db,p,1,1,0;}"
    : "+f"(d[0]),"+f"(d[1]),"+f"(d[2]),"+f"(d[3]),"+f"(d[4]),"+f"(d[5]),"+f"(d[6]),"+f"(d[7]),"+f"(d[8]),"+f"(d[9]),"+f"(d[10]),"+f"(d[11]),"+f"(d[12]),"+f"(d[13]),"+f"(d[14]),"+f"(d[15]),"+f"(d[16]),"+f"(d[17]),"+f"(d[18]),"+f"(d[19]),"+f"(d[20]),"+f"(d[21]),"+f"(d[22]),"+f"(d[23]),"+f"(d[24]),"+f"(d[25]),"+f"(d[26]),"+f"(d[27]),"+f"(d[28]),"+f"(d[29]),"+f"(d[30]),"+f"(d[31])
    : "r"(a0),"r"(a1),"r"(a2),"r"(a3),"r"(lb),"n"(OB),"n"(HB),"n"(SD));
} };
template<> struct WgRS<96,0> { template<int OB, unsigned HB, int SD> static __device__ __forceinline__ void run(float* d, uint32_t a0, uint32_t a1, uint32_t a2, uint32_t a3, uint32_t lb) {
  asm volatile("{.reg .pred p; .reg .b32 t; .reg .b64 db; add.s32 t,%52,%53; mov.b64 db,{t,%54}; setp.ne.b32 p,%55,0; wgmma.mma_async.sync.aligned.m64n96k16.f32.bf16.bf16 {%0,%1,%2,%3,%4,%5,%6,%7,%8,%9,%10,%11,%12,%13,%14,%15,%16,%17,%18,%19,%20,%21,%22,%23,%24,%25,%26,%27,%28,%29,%30,%31,%32,%33,%34,%35,%36,%37,%38,%39,%40,%41,%42,%43,%44,%45,%46,%47},{%48,%49,%50,%51},db,p,1,1,0;}"
    : "+f"(d[0]),"+f"(d[1]),"+f"(d[2]),"+f"(d[3]),"+f"(d[4]),"+f"(d[5]),"+f"(d[6]),"+f"(d[7]),"+f"(d[8]),"+f"(d[9]),"+f"(d[10]),"+f"(d[11]),"+f"(d[12]),"+f"(d[13]),"+f"(d[14]),"+f"(d[15]),"+f"(d[16]),"+f"(d[17]),"+f"(d[18]),"+f"(d[19]),"+f"(d[20]),"+f"(d[21]),"+f"(d[22]),"+f"(d[23]),"+f"(d[24]),"+f"(d[25]),"+f"(d[26]),"+f"(d[27]),"+f"(d[28]),"+f"(d[29]),"+f"(d[30]),"+f"(d[31]),"+f"(d[32]),"+f"(d[33]),"+f"(d[34]),"+f"(d[35]),"+f"(d[36]),"+f"(d[37]),"+f"(d[38]),"+f"(d[39]),"+f"(d[40]),"+f"(d[41]),"+f"(d[42]),"+f"(d[43]),"+f"(d[44]),"+f"(d[45]),"+f"(d[46]),"+f"(d[47])
    : "r"(a0),"r"(a1),"r"(a2),"r"(a3),"r"(lb),"n"(OB),"n"(HB),"n"(SD));
} };
template<> struct WgRS<128,0> { template<int OB, unsigned HB, int SD> static __device__ __forceinline__ void run(float* d, uint32_t a0, uint32_t a1, uint32_t a2, uint32_t a3, uint32_t lb) {
  asm volatile("{.reg .pred p; .reg .b32 t; .reg .b64 db; add.s32 t,%68,%69; mov.b64 db,{t,%70}; setp.ne.b32 p,%71,0; wgmma.mma_async.sync.aligned.m64n128k16.f32.bf16.bf16 {%0,%1,%2,%3,%4,%5,%6,%7,%8,%9,%10,%11,%12,%13,%14,%15,%16,%17,%18,%19,%20,%21,%22,%23,%24,%25,%26,%27,%28,%29,%30,%31,%32,%33,%34,%35,%36,%37,%38,%39,%40,%41,%42,%43,%44,%45,%46,%47,%48,%49,%50,%51,%52,%53,%54,%55,%56,%57,%58,%59,%60,%61,%62,%63},{%64,%65,%66,%67},db,p,1,1,0;}"
    : "+f"(d[0]),"+f"(d[1]),"+f"(d[2]),"+f"(d[3]),"+f"(d[4]),"+f"(d[5]),"+f"(d[6]),"+f"(d[7]),"+f"(d[8]),"+f"(d[9]),"+f"(d[10]),"+f"(d[11]),"+f"(d[12]),"+f"(d[13]),"+f"(d[14]),"+f"(d[15]),"+f"(d[16]),"+f"(d[17]),"+f"(d[18]),"+f"(d[19]),"+f"(d[20]),"+f"(d[21]),"+f"(d[22]),"+f"(d[23]),"+f"(d[24]),"+f"(d[25]),"+f"(d[26]),"+f"(d[27]),"+f"(d[28]),"+f"(d[29]),"+f"(d[30]),"+f"(d[31]),"+f"(d[32]),"+f"(d[33]),"+f"(d[34]),"+f"(d[35]),"+f"(d[36]),"+f"(d[37]),"+f"(d[38]),"+f"(d[39]),"+f"(d[40]),"+f"(d[41]),"+f"(d[42]),"+f"(d[43]),"+f"(d[44]),"+f"(d[45]),"+f"(d[46]),"+f"(d[47]),"+f"(d[48]),"+f"(d[49]),"+f"(d[50]),"+f"(d[51]),"+f"(d[52]),"+f"(d[53]),"+f"(d[54]),"+f"(d[55]),"+f"(d[56]),"+f"(d[57]),"+f"(d[58]),"+f"(d[59]),"+f"(d[60]),"+f"(d[61]),"+f"(d[62]),"+f"(d[63])
    : "r"(a0),"r"(a1),"r"(a2),"r"(a3),"r"(lb),"n"(OB),"n"(HB),"n"(SD));
} };
template<> struct WgRS<128,1> { template<int OB, unsigned HB, int SD> static __device__ __forceinline__ void run(float* d, uint32_t a0, uint32_t a1, uint32_t a2, uint32_t a3, uint32_t lb) {
  asm volatile("{.reg .pred p; .reg .b32 t; .reg .b64 db; add.s32 t,%68,%69; mov.b64 db,{t,%70}; setp.ne.b32 p,%71,0; wgmma.mma_async.sync.aligned.m64n128k16.f32.bf16.bf16 {%0,%1,%2,%3,%4,%5,%6,%7,%8,%9,%10,%11,%12,%13,%14,%15,%16,%17,%18,%19,%20,%21,%22,%23,%24,%25,%26,%27,%28,%29,%30,%31,%32,%33,%34,%35,%36,%37,%38,%39,%40,%41,%42,%43,%44,%45,%46,%47,%48,%49,%50,%51,%52,%53,%54,%55,%56,%57,%58,%59,%60,%61,%62,%63},{%64,%65,%66,%67},db,p,1,1,1;}"
    : "+f"(d[0]),"+f"(d[1]),"+f"(d[2]),"+f"(d[3]),"+f"(d[4]),"+f"(d[5]),"+f"(d[6]),"+f"(d[7]),"+f"(d[8]),"+f"(d[9]),"+f"(d[10]),"+f"(d[11]),"+f"(d[12]),"+f"(d[13]),"+f"(d[14]),"+f"(d[15]),"+f"(d[16]),"+f"(d[17]),"+f"(d[18]),"+f"(d[19]),"+f"(d[20]),"+f"(d[21]),"+f"(d[22]),"+f"(d[23]),"+f"(d[24]),"+f"(d[25]),"+f"(d[26]),"+f"(d[27]),"+f"(d[28]),"+f"(d[29]),"+f"(d[30]),"+f"(d[31]),"+f"(d[32]),"+f"(d[33]),"+f"(d[34]),"+f"(d[35]),"+f"(d[36]),"+f"(d[37]),"+f"(d[38]),"+f"(d[39]),"+f"(d[40]),"+f"(d[41]),"+f"(d[42]),"+f"(d[43]),"+f"(d[44]),"+f"(d[45]),"+f"(d[46]),"+f"(d[47]),"+f"(d[48]),"+f"(d[49]),"+f"(d[50]),"+f"(d[51]),"+f"(d[52]),"+f"(d[53]),"+f"(d[54]),"+f"(d[55]),"+f"(d[56]),"+f"(d[57]),"+f"(d[58]),"+f"(d[59]),"+f"(d[60]),"+f"(d[61]),"+f"(d[62]),"+f"(d[63])
    : "r"(a0),"r"(a1),"r"(a2),"r"(a3),"r"(lb),"n"(OB),"n"(HB),"n"(SD));
} };
template<> struct WgRS<192,1> { template<int OB, unsigned HB, int SD> static __device__ __forceinline__ void run(float* d, uint32_t a0, uint32_t a1, uint32_t a2, uint32_t a3, uint32_t lb) {
  asm volatile("{.reg .pred p; .reg .b32 t; .reg .b64 db; add.s32 t,%100,%101; mov.b64 db,{t,%102}; setp.ne.b32 p,%103,0; wgmma.mma_async.sync.aligned.m64n192k16.f32.bf16.bf16 {%0,%1,%2,%3,%4,%5,%6,%7,%8,%9,%10,%11,%12,%13,%14,%15,%16,%17,%18,%19,%20,%21,%22,%23,%24,%25,%26,%27,%28,%29,%30,%31,%32,%33,%34,%35,%36,%37,%38,%39,%40,%41,%42,%43,%44,%45,%46,%47,%48,%49,%50,%51,%52,%53,%54,%55,%56,%57,%58,%59,%60,%61,%62,%63,%64,%65,%66,%67,%68,%69,%70,%71,%72,%73,%74,%75,%76,%77,%78,%79,%80,%81,%82,%83,%84,%85,%86,%87,%88,%89,%90,%91,%92,%93,%94,%95},{%96,%97,%98,%99},db,p,1,1,1;}"
    : "+f"(d[0]),"+f"(d[1]),"+f"(d[2]),"+f"(d[3]),"+f"(d[4]),"+f"(d[5]),"+f"(d[6]),"+f"(d[7]),"+f"(d[8]),"+f"(d[9]),"+f"(d[10]),"+f"(d[11]),"+f"(d[12]),"+f"(d[13]),"+f"(d[14]),"+f"(d[15]),"+f"(d[16]),"+f"(d[17]),"+f"(d[18]),"+f"(d[19]),"+f"(d[20]),"+f"(d[21]),"+f"(d[22]),"+f"(d[23]),"+f"(d[24]),"+f"(d[25]),"+f"(d[26]),"+f"(d[27]),"+f"(d[28]),"+f"(d[29]),"+f"(d[30]),"+f"(d[31]),"+f"(d[32]),"+f"(d[33]),"+f"(d[34]),"+f"(d[35]),"+f"(d[36]),"+f"(d[37]),"+f"(d[38]),"+f"(d[39]),"+f"(d[40]),"+f"(d[41]),"+f"(d[42]),"+f"(d[43]),"+f"(d[44]),"+f"(d[45]),"+f"(d[46]),"+f"(d[47]),"+f"(d[48]),"+f"(d[49]),"+f"(d[50]),"+f"(d[51]),"+f"(d[52]),"+f"(d[53]),"+f"(d[54]),"+f"(d[55]),"+f"(d[56]),"+f"(d[57]),"+f"(d[58]),"+f"(d[59]),"+f"(d[60]),"+f"(d[61]),"+f"(d[62]),"+f"(d[63]),"+f"(d[64]),"+f"(d[65]),"+f"(d[66]),"+f"(d[67]),"+f"(d[68]),"+f"(d[69]),"+f"(d[70]),"+f"(d[71]),"+f"(d[72]),"+f"(d[73]),"+f"(d[74]),"+f"(d[75]),"+f"(d[76]),"+f"(d[77]),"+f"(d[78]),"+f"(d[79]),"+f"(d[80]),"+f"(d[81]),"+f"(d[82]),"+f"(d[83]),"+f"(d[84]),"+f"(d[85]),"+f"(d[86]),"+f"(d[87]),"+f"(d[88]),"+f"(d[89]),"+f"(d[90]),"+f"(d[91]),"+f"(d[92]),"+f"(d[93]),"+f"(d[94]),"+f"(d[95])
    : "r"(a0),"r"(a1),"r"(a2),"r"(a3),"r"(lb),"n"(OB),"n"(HB),"n"(SD));
} };
template<> struct WgSS<128,1> { template<int OA, unsigned HA, int OB, unsigned HB, int SD> static __device__ __forceinline__ void run(float* d, uint32_t la, uint32_t lb) {
  asm volatile("{.reg .pred p; .reg .b32 t,u; .reg .b64 da,db; add.s32 t,%64,%65; mov.b64 da,{t,%66}; add.s32 u,%67,%68; mov.b64 db,{u,%69}; setp.ne.b32 p,%70,0; wgmma.mma_async.sync.aligned.m64n128k16.f32.bf16.bf16 {%0,%1,%2,%3,%4,%5,%6,%7,%8,%9,%10,%11,%12,%13,%14,%15,%16,%17,%18,%19,%20,%21,%22,%23,%24,%25,%26,%27,%28,%29,%30,%31,%32,%33,%34,%35,%36,%37,%38,%39,%40,%41,%42,%43,%44,%45,%46,%47,%48,%49,%50,%51,%52,%53,%54,%55,%56,%57,%58,%59,%60,%61,%62,%63},da,db,p,1,1,0,1;}"
    : "+f"(d[0]),"+f"(d[1]),"+f"(d[2]),"+f"(d[3]),"+f"(d[4]),"+f"(d[5]),"+f"(d[6]),"+f"(d[7]),"+f"(d[8]),"+f"(d[9]),"+f"(d[10]),"+f"(d[11]),"+f"(d[12]),"+f"(d[13]),"+f"(d[14]),"+f"(d[15]),"+f"(d[16]),"+f"(d[17]),"+f"(d[18]),"+f"(d[19]),"+f"(d[20]),"+f"(d[21]),"+f"(d[22]),"+f"(d[23]),"+f"(d[24]),"+f"(d[25]),"+f"(d[26]),"+f"(d[27]),"+f"(d[28]),"+f"(d[29]),"+f"(d[30]),"+f"(d[31]),"+f"(d[32]),"+f"(d[33]),"+f"(d[34]),"+f"(d[35]),"+f"(d[36]),"+f"(d[37]),"+f"(d[38]),"+f"(d[39]),"+f"(d[40]),"+f"(d[41]),"+f"(d[42]),"+f"(d[43]),"+f"(d[44]),"+f"(d[45]),"+f"(d[46]),"+f"(d[47]),"+f"(d[48]),"+f"(d[49]),"+f"(d[50]),"+f"(d[51]),"+f"(d[52]),"+f"(d[53]),"+f"(d[54]),"+f"(d[55]),"+f"(d[56]),"+f"(d[57]),"+f"(d[58]),"+f"(d[59]),"+f"(d[60]),"+f"(d[61]),"+f"(d[62]),"+f"(d[63])
    : "r"(la),"n"(OA),"n"(HA),"r"(lb),"n"(OB),"n"(HB),"n"(SD));
} };
template<> struct WgSS<192,1> { template<int OA, unsigned HA, int OB, unsigned HB, int SD> static __device__ __forceinline__ void run(float* d, uint32_t la, uint32_t lb) {
  asm volatile("{.reg .pred p; .reg .b32 t,u; .reg .b64 da,db; add.s32 t,%96,%97; mov.b64 da,{t,%98}; add.s32 u,%99,%100; mov.b64 db,{u,%101}; setp.ne.b32 p,%102,0; wgmma.mma_async.sync.aligned.m64n192k16.f32.bf16.bf16 {%0,%1,%2,%3,%4,%5,%6,%7,%8,%9,%10,%11,%12,%13,%14,%15,%16,%17,%18,%19,%20,%21,%22,%23,%24,%25,%26,%27,%28,%29,%30,%31,%32,%33,%34,%35,%36,%37,%38,%39,%40,%41,%42,%43,%44,%45,%46,%47,%48,%49,%50,%51,%52,%53,%54,%55,%56,%57,%58,%59,%60,%61,%62,%63,%64,%65,%66,%67,%68,%69,%70,%71,%72,%73,%74,%75,%76,%77,%78,%79,%80,%81,%82,%83,%84,%85,%86,%87,%88,%89,%90,%91,%92,%93,%94,%95},da,db,p,1,1,0,1;}"
    : "+f"(d[0]),"+f"(d[1]),"+f"(d[2]),"+f"(d[3]),"+f"(d[4]),"+f"(d[5]),"+f"(d[6]),"+f"(d[7]),"+f"(d[8]),"+f"(d[9]),"+f"(d[10]),"+f"(d[11]),"+f"(d[12]),"+f"(d[13]),"+f"(d[14]),"+f"(d[15]),"+f"(d[16]),"+f"(d[17]),"+f"(d[18]),"+f"(d[19]),"+f"(d[20]),"+f"(d[21]),"+f"(d[22]),"+f"(d[23]),"+f"(d[24]),"+f"(d[25]),"+f"(d[26]),"+f"(d[27]),"+f"(d[28]),"+f"(d[29]),"+f"(d[30]),"+f"(d[31]),"+f"(d[32]),"+f"(d[33]),"+f"(d[34]),"+f"(d[35]),"+f"(d[36]),"+f"(d[37]),"+f"(d[38]),"+f"(d[39]),"+f"(d[40]),"+f"(d[41]),"+f"(d[42]),"+f"(d[43]),"+f"(d[44]),"+f"(d[45]),"+f"(d[46]),"+f"(d[47]),"+f"(d[48]),"+f"(d[49]),"+f"(d[50]),"+f"(d[51]),"+f"(d[52]),"+f"(d[53]),"+f"(d[54]),"+f"(d[55]),"+f"(d[56]),"+f"(d[57]),"+f"(d[58]),"+f"(d[59]),"+f"(d[60]),"+f"(d[61]),"+f"(d[62]),"+f"(d[63]),"+f"(d[64]),"+f"(d[65]),"+f"(d[66]),"+f"(d[67]),"+f"(d[68]),"+f"(d[69]),"+f"(d[70]),"+f"(d[71]),"+f"(d[72]),"+f"(d[73]),"+f"(d[74]),"+f"(d[75]),"+f"(d[76]),"+f"(d[77]),"+f"(d[78]),"+f"(d[79]),"+f"(d[80]),"+f"(d[81]),"+f"(d[82]),"+f"(d[83]),"+f"(d[84]),"+f"(d[85]),"+f"(d[86]),"+f"(d[87]),"+f"(d[88]),"+f"(d[89]),"+f"(d[90]),"+f"(d[91]),"+f"(d[92]),"+f"(d[93]),"+f"(d[94]),"+f"(d[95])
    : "r"(la),"n"(OA),"n"(HA),"r"(lb),"n"(OB),"n"(HB),"n"(SD));
} };


namespace {

constexpr int SEQ = 2048, DM = 512, FF = 1792;
constexpr int NI = 4;
constexpr int CUT1 = 0x3333;
constexpr int CUT2 = 0x2231;
constexpr int CUT3 = 0x2321;
constexpr int Q1D = 1000;
constexpr int WIT = 0x23222;
constexpr int WMIN = 2;
constexpr int WW = 0;
constexpr int LAGS = 45;
constexpr unsigned AD0 = 900;
constexpr unsigned AD1 = 700;
constexpr int CREG = 216;
constexpr int GREG = 240;
constexpr int PERT = 0;
constexpr int NCTA = 128;
constexpr int SPIN_LIMIT = 200000;

constexpr int SM_A    = 0;
constexpr int SM_W    = 131072;
constexpr int SM_BAR  = SM_W + 6 * 16384;
constexpr int SM_TOTAL = SM_BAR + 1024 + 1024;
constexpr int CV_T = 0, CV_TS = 8256;
constexpr int CV_Z = 16512, CV_ZS = 4480, CV_ZC = 2240;
constexpr int CV_R = 32768;
constexpr int B_KV = 0, B_Z = 32, B_Q = 48;
constexpr int B_PFULL = 56, B_WFULL = 120, B_HFULL = 168, B_AFULL = 264, B_RETRY = 376;
constexpr int B_WEMPTY = 392, B_HEMPTY = 440, B_PREADY = 544;
constexpr int B_VALID = 552, B_AF2 = 864, B_Y = 880;
constexpr int B_T = 888, B_YW = 920;

struct __align__(1024) Scratch {
  uint4 y[131072];
  uint4 a[131072];
  uint4 h[16 * 8 * 2 * 14 * 128];
  uint2 ma[16 * 8 * 8 * 32];
  uint2 mb[16 * 8 * 8 * 8];
  unsigned epoch[NCTA];
};
__device__ Scratch g_scratch;
#define g_s (*P.gs)


__device__ __forceinline__ uint32_t smem_u32(const void* p) { return (uint32_t)__cvta_generic_to_shared(p); }
__device__ __forceinline__ uint32_t mapa(uint32_t a, uint32_t r) { uint32_t d; asm("mapa.shared::cluster.u32 %0, %1, %2;" : "=r"(d) : "r"(a), "r"(r)); return d; }
__device__ __forceinline__ void mbar_init(uint32_t a, uint32_t c) { asm volatile("mbarrier.init.shared::cta.b64 [%0], %1;" :: "r"(a), "r"(c) : "memory"); }
__device__ __forceinline__ void mbar_expect(uint32_t a, uint32_t b) { asm volatile("mbarrier.arrive.expect_tx.shared::cta.b64 _, [%0], %1;" :: "r"(a), "r"(b) : "memory"); }
__device__ __forceinline__ void mbar_arrive(uint32_t a) { asm volatile("mbarrier.arrive.shared::cta.b64 _, [%0];" :: "r"(a) : "memory"); }
__device__ __forceinline__ void mbar_arrive_remote(uint32_t a) { asm volatile("mbarrier.arrive.shared::cluster.b64 _, [%0];" :: "r"(a) : "memory"); }
__device__ __forceinline__ void mbar_wait(uint32_t a, uint32_t p) {
  asm volatile("{.reg .pred P; .reg .u32 n; mov.u32 n, 0;\n"
               "W: mbarrier.try_wait.parity.shared::cta.b64 P, [%0], %1; @P bra D;\n"
               "add.u32 n, n, 1; setp.lt.u32 P, n, 100000; @P bra W;\n"
               "D: }" :: "r"(a), "r"(p) : "memory");
}
__device__ __forceinline__ bool elect() { uint32_t p; asm volatile("{.reg .pred P; elect.sync _|P, 0xffffffff; selp.u32 %0, 1, 0, P;}" : "=r"(p)); return p; }
__device__ __forceinline__ int lane_now() { int l; asm volatile("mov.u32 %0, %%laneid;" : "=r"(l)); return l; }
__device__ __forceinline__ void bar_sync(int id, int n) { asm volatile("bar.sync %0, %1;" :: "r"(id), "r"(n) : "memory"); }
__device__ __forceinline__ void bar_arrive(int id, int n) { asm volatile("bar.arrive %0, %1;" :: "r"(id), "r"(n) : "memory"); }
__device__ __forceinline__ void wg_fence() { asm volatile("wgmma.fence.sync.aligned;" ::: "memory"); }
__device__ __forceinline__ void wg_commit() { asm volatile("wgmma.commit_group.sync.aligned;" ::: "memory"); }
template<int N> __device__ __forceinline__ void wg_wait() { asm volatile("wgmma.wait_group.sync.aligned %0;" :: "n"(N) : "memory"); }
template<int N> __device__ __forceinline__ void pin(float* d) {
#pragma unroll
  for (int i = 0; i < N; i++) asm volatile("" : "+f"(d[i]) :: "memory");
}
template<int N> __device__ __forceinline__ void pinr(uint32_t* d) {
#pragma unroll
  for (int i = 0; i < N; i++) asm volatile("" : "+r"(d[i]) :: "memory");
}
__device__ __forceinline__ void fence_async_smem() { asm volatile("fence.proxy.async.shared::cta;" ::: "memory"); }
__device__ __forceinline__ uint32_t dlo(uint32_t addr) { return (addr & 0x3FFFF) >> 4; }
__host__ __device__ constexpr int doff(int bytes, int lbo) { return bytes / 16 + ((lbo / 16) << 16); }
__host__ __device__ constexpr unsigned dhi(int sbo, unsigned sw) { return (unsigned)(sbo / 16) | (sw << 30); }
template<int V> struct IC { static constexpr int v = V; };
template<int I, int N, class F> __device__ __forceinline__ void sfor(F&& f) {
  if constexpr (I < N) { f(IC<I>{}); sfor<I + 1, N>(f); }
}
#define SFOR(var, lo, hi) sfor<lo, hi>([&](auto var##_) { constexpr int var = decltype(var##_)::v;
__device__ __forceinline__ uint32_t pack2(float lo, float hi) { uint32_t r; asm("cvt.rn.bf16x2.f32 %0, %1, %2;" : "=r"(r) : "f"(hi), "f"(lo)); return r; }
__device__ __forceinline__ float blo(uint32_t v) { return __uint_as_float(v << 16); }
__device__ __forceinline__ float bhi(uint32_t v) { return __uint_as_float(v & 0xffff0000u); }
__device__ __forceinline__ uint32_t tagw(uint32_t v, uint32_t m, uint32_t tag) { return (v & ~m) | (tag & m); }
__device__ __forceinline__ uint32_t lds32(uint32_t a) { uint32_t v; asm volatile("ld.shared.b32 %0, [%1];" : "=r"(v) : "r"(a) : "memory"); return v; }
__device__ __forceinline__ uint4 lds128(uint32_t a) { uint4 v; asm volatile("ld.shared.v4.b32 {%0,%1,%2,%3}, [%4];" : "=r"(v.x), "=r"(v.y), "=r"(v.z), "=r"(v.w) : "r"(a) : "memory"); return v; }
__device__ __forceinline__ void sts128(uint32_t a, uint32_t x, uint32_t y, uint32_t z, uint32_t w) { asm volatile("st.shared.v4.b32 [%0], {%1,%2,%3,%4};" :: "r"(a), "r"(x), "r"(y), "r"(z), "r"(w) : "memory"); }
__device__ __forceinline__ void stsm4(uint32_t a, uint32_t x, uint32_t y, uint32_t z, uint32_t w) { asm volatile("stmatrix.sync.aligned.m8n8.x4.shared.b16 [%0], {%1,%2,%3,%4};" :: "r"(a), "r"(x), "r"(y), "r"(z), "r"(w) : "memory"); }
__device__ __forceinline__ void stg_ll128(void* p, uint32_t x, uint32_t y, uint32_t z, uint32_t w) { asm volatile("st.relaxed.gpu.global.v4.u32 [%0], {%1,%2,%3,%4};" :: "l"(p), "r"(x), "r"(y), "r"(z), "r"(w) : "memory"); }
__device__ __forceinline__ uint2 ldg_ll64(const void* p) { uint2 v; asm volatile("ld.relaxed.gpu.global.v2.u32 {%0,%1}, [%2];" : "=r"(v.x), "=r"(v.y) : "l"(p) : "memory"); return v; }
__device__ __forceinline__ void ldg_ll64_if(uint2& v, const void* p, uint32_t bad) {
  asm volatile("{.reg .pred p; setp.ne.u32 p, %3, 0; @p ld.relaxed.gpu.global.v2.u32 {%0,%1}, [%2];}" : "+r"(v.x), "+r"(v.y) : "l"(p), "r"(bad) : "memory");
}
__device__ __forceinline__ void stg_ll64(void* p, uint32_t x, uint32_t y) { asm volatile("st.relaxed.gpu.global.v2.u32 [%0], {%1,%2};" :: "l"(p), "r"(x), "r"(y) : "memory"); }
__device__ __forceinline__ uint32_t hfma2(uint32_t a, uint32_t b, uint32_t c) { uint32_t d; asm("fma.rn.bf16x2 %0, %1, %2, %3;" : "=r"(d) : "r"(a), "r"(b), "r"(c)); return d; }
__device__ __forceinline__ uint32_t hmul2(uint32_t a, uint32_t b) { uint32_t d; asm("mul.rn.bf16x2 %0, %1, %2;" : "=r"(d) : "r"(a), "r"(b)); return d; }
__device__ __forceinline__ float glu(float g, float u, float c) { float t; asm("tanh.approx.f32 %0, %1;" : "=f"(t) : "f"(c * g)); return fmaf(t, u, u); }
__device__ __forceinline__ void tma3(uint32_t dst, const CUtensorMap* m, uint32_t bar, int x, int y, int z) {
  asm volatile("cp.async.bulk.tensor.3d.shared::cluster.global.mbarrier::complete_tx::bytes [%0], [%1, {%3, %4, %5}], [%2];" :: "r"(dst), "l"(m), "r"(bar), "r"(x), "r"(y), "r"(z) : "memory");
}
__device__ __forceinline__ uint2 lds64(uint32_t a) { uint2 v; asm volatile("ld.shared.v2.b32 {%0,%1}, [%2];" : "=r"(v.x), "=r"(v.y) : "r"(a) : "memory"); return v; }
__device__ __forceinline__ void ldsm4(uint32_t a, uint32_t& x, uint32_t& y, uint32_t& z, uint32_t& w) { asm volatile("ldmatrix.sync.aligned.m8n8.x4.shared.b16 {%0,%1,%2,%3}, [%4];" : "=r"(x), "=r"(y), "=r"(z), "=r"(w) : "r"(a) : "memory"); }
__device__ __forceinline__ void tma2(uint32_t dst, const CUtensorMap* m, uint32_t bar, int x, int y) {
  asm volatile("cp.async.bulk.tensor.2d.shared::cluster.global.mbarrier::complete_tx::bytes [%0], [%1, {%3, %4}], [%2];" :: "r"(dst), "l"(m), "r"(bar), "r"(x), "r"(y) : "memory");
}
__device__ __forceinline__ void bulk_load(uint32_t dst, const void* src, uint32_t bytes, uint32_t bar) {
  asm volatile("cp.async.bulk.shared::cluster.global.mbarrier::complete_tx::bytes [%0], [%1], %2, [%3];" :: "r"(dst), "l"(src), "r"(bytes), "r"(bar) : "memory");
}
__device__ __forceinline__ void bulk_load_mc(uint32_t dst, const void* src, uint32_t bytes, uint32_t bar) {
  asm volatile("cp.async.bulk.shared::cluster.global.mbarrier::complete_tx::bytes.multicast::cluster [%0], [%1], %2, [%3], %4;" :: "r"(dst), "l"(src), "r"(bytes), "r"(bar), "h"((uint16_t)3) : "memory");
}
__device__ __forceinline__ void l2_prefetch(const void* p, uint32_t bytes) { asm volatile("cp.async.bulk.prefetch.L2.global [%0], %1;" :: "l"(p), "r"(bytes) : "memory"); }

__host__ __device__ constexpr int cut(unsigned long long d, int i) { int r = 0; for (int k = 0; k < i; k++) { r += d & 15; d >>= 4; } return r; }
__host__ __device__ constexpr int cut1(int i) { return cut(CUT1, i); }
__host__ __device__ constexpr int cut2(int i) { return cut(CUT2, i); }
__host__ __device__ constexpr int cut3(int i) { return cut(CUT3, i); }

struct Params {
  const __nv_bfloat16 *k, *v, *sk, *zk, *dd;
  Scratch* gs;
  uint32_t zero;
  const __nv_bfloat16 *q, *wg, *wu, *wd;
  __nv_bfloat16* out;
};

constexpr int KV_PL = 1040, KV_V = 4224;
__device__ __forceinline__ void kv_produce(uint32_t cur, uint32_t t0, bool local, uint32_t rbar, const uint32_t (&w0)[4], const uint32_t (&w1)[4]) {
  uint2 kr[8], vr[5];
#pragma unroll
  for (int i = 0; i < 4; i++) { kr[i] = lds64(cur - 16 + i * KV_PL); kr[4 + i] = lds64(cur + i * KV_PL); vr[1 + i] = lds64(cur + KV_V + i * KV_PL); }
  vr[0] = lds64(cur - 16 + KV_V + 3 * KV_PL);
  uint32_t a[2][5];
#pragma unroll
  for (int i = 0; i < 5; i++) {
    uint32_t x = hmul2(kr[i].x, w0[3]); x = hfma2(kr[i + 1].x, w0[2], x); x = hfma2(kr[i + 2].x, w0[1], x); x = hfma2(kr[i + 3].x, w0[0], x);
    uint32_t y = hmul2(kr[i].y, w1[3]); y = hfma2(kr[i + 1].y, w1[2], y); y = hfma2(kr[i + 2].y, w1[1], y); y = hfma2(kr[i + 3].y, w1[0], y);
    a[0][i] = hmul2(x, vr[i].x); a[1][i] = hmul2(y, vr[i].y);
  }
  uint32_t o[4][4];
#pragma unroll
  for (int c = 0; c < 4; c++)
#pragma unroll
    for (int i = 0; i < 4; i++) o[c][i] = __byte_perm(a[c >> 1][i + 1], a[c >> 1][i], (c & 1) ? 0x7632 : 0x5410);
  if (!local) {
#pragma unroll
    for (int c = 0; c < 4; c++)
      asm volatile("st.async.weak.shared::cluster.mbarrier::complete_tx::bytes.v4.b32 [%0], {%1,%2,%3,%4}, [%5];"
                   :: "r"(t0 + (c >> 1) * 65536 + (c & 1) * CV_TS), "r"(o[c][0]), "r"(o[c][1]), "r"(o[c][2]), "r"(o[c][3]), "r"(rbar) : "memory");
  } else {
#pragma unroll
    for (int c = 0; c < 4; c++) sts128(t0 + (c >> 1) * 65536 + (c & 1) * CV_TS, o[c][0], o[c][1], o[c][2], o[c][3]);
  }
}

__host__ __device__ constexpr int h_off(int q) { return q < 6 ? q * 6144 : q < 9 ? q * 8192 - 12288 : q == 9 ? 0 : (q - 8) * 8192; }
__host__ __device__ constexpr int h_go(int q) { return q < 9 ? 25 + q : 30 + q; }
constexpr int O_PART = 36864, O_Y = 8192;
__device__ __forceinline__ const uint4* h_src(const Params& P, int tile, int cf, int q) {
  const int m = q < 6 ? 1 + (q >> 1) : q < 9 ? q - 5 : q - 8;
  return g_s.h + (tile * 8 + (cf ^ m)) * 3584 + (q < 6 ? (q & 1) * 384 : q < 9 ? 768 : 1280);
}

struct ConvCtx {
  uint32_t id, tb, ta, rw, rr[3], dz, ym, yn, yt; float zero; uint2* yp; uint4* yq; int wg, warp;
};
template<int I> __device__ __forceinline__ void conv_load(uint32_t (&f)[2][8], uint32_t ta) {
#pragma unroll
  for (int c = 0; c < 2; c++) {
    const uint32_t a = ta + c * CV_TS + (512 * (I / 4) + 32 * (I % 4)) * 4;
    if constexpr (I % 4 == 0) f[c][2] = lds32(a);
    f[c][0] = lds32(a + 32); f[c][1] = lds32(a + 64); f[c][4] = lds32(a + 96); f[c][5] = lds32(a + 128);
  }
}
template<int C> __device__ __forceinline__ void conv_send(float (&acc)[2][64], const ConvCtx& X) {
#pragma unroll
  for (int v = 1; v < 4; v++) {
    const float* p = &acc[0][60 - 16 * C - 4 * v]; const float* q = &acc[1][60 - 16 * C - 4 * v];
    if (C < 3 || v + X.warp < 4) sts128(X.rw + (3 * C + v - 1) * 512, pack2(p[0], p[1]), pack2(q[0], q[1]), pack2(p[2], p[3]), pack2(q[2], q[3]));
  }
}
template<int C> __device__ __forceinline__ void conv_fetch(uint4 (&r)[3], const ConvCtx& X) {
  bar_sync(3 + X.wg, 128);
#pragma unroll
  for (int v = 1; v < 4; v++) {
    if (C == 0) { r[v - 1] = make_uint4(0, 0, 0, 0); if (X.warp >= v) r[v - 1] = lds128(X.rr[v - 1]); }
    else r[v - 1] = lds128(X.rr[v - 1] + C * 1536);
  }
}
__device__ __forceinline__ void mma16816(float (&d)[4], uint32_t a0, uint32_t a1, uint32_t a2, uint32_t a3, uint32_t b0, uint32_t b1) {
  asm("mma.sync.aligned.m16n8k16.row.col.f32.bf16.bf16.f32 {%0,%1,%2,%3}, {%4,%5,%6,%7}, {%8,%9}, {%0,%1,%2,%3};"
      : "+f"(d[0]), "+f"(d[1]), "+f"(d[2]), "+f"(d[3]) : "r"(a0), "r"(a1), "r"(a2), "r"(a3), "r"(b0), "r"(b1));
}
__device__ __forceinline__ void add_tile(float (&d)[4], uint32_t id, uint32_t b0, uint32_t b1) { mma16816(d, id, 0, 0, id, b0, b1); }
template<int C> __device__ __forceinline__ void conv_publish(float (&acc)[2][64], const uint4 (&r)[3], const ConvCtx& X) {
  const float* u = &acc[0][60 - 16 * C]; const float* v = &acc[1][60 - 16 * C];
  if (C == 3) {
    float p[4] = {0.f, 0.f, 0.f, 0.f}, q[4] = {0.f, 0.f, 0.f, 0.f};
    add_tile(p, X.id, pack2(u[0], u[1]), pack2(v[0], v[1])); add_tile(q, X.id, pack2(u[2], u[3]), pack2(v[2], v[3]));
#pragma unroll
    for (int i = 0; i < 3; i++) { add_tile(p, X.id, r[i].x, r[i].y); add_tile(q, X.id, r[i].z, r[i].w); }
    stg_ll128(X.yq + C * 32768, tagw(pack2(p[0], p[2]), X.yn, X.yt), pack2(q[0], q[2]), pack2(p[1], p[3]), pack2(q[1], q[3]));
  } else {
#define S4(c, g, f) (c + g(r[0].f)) + (g(r[1].f) + g(r[2].f))
    stg_ll64(X.yp + C * 65536, tagw(pack2(S4(u[0], blo, x), S4(v[0], blo, y)), X.ym, X.yt), pack2(S4(u[2], blo, z), S4(v[2], blo, w)));
    stg_ll64(X.yp + C * 65536 - 2048, tagw(pack2(S4(u[1], bhi, x), S4(v[1], bhi, y)), X.ym, X.yt), pack2(S4(u[3], bhi, z), S4(v[3], bhi, w)));
#undef S4
  }
}
__device__ __forceinline__ uint32_t fcopy(uint32_t x, float nzero) { return __float_as_uint(__fadd_rn(__uint_as_float(x), nzero)); }
template<int I> __device__ __forceinline__ void conv_dup(uint32_t (&ff)[16][2][8], float zero) {
#pragma unroll
  for (int c = 0; c < 2; c++) {
    uint32_t* f = ff[I][c];
    if constexpr (I % 4 != 0) f[2] = fcopy(ff[I - 1][c][5], zero);
    f[3] = fcopy(f[0], zero); f[6] = fcopy(f[1], zero); f[7] = fcopy(f[4], zero); pinr<8>(f);
  }
}
template<int I> struct ConvStep {
  static __device__ __forceinline__ void run(float (&acc)[2][64], uint32_t (&ff)[16][2][8], uint4 (&r)[3], ConvCtx& X) {
    constexpr int C = I / 4, M = 2 * (I % 4);
    constexpr int D = I < 8 ? 1 : 2;
    uint32_t (&f)[2][8] = ff[I];
    conv_dup<I>(ff, X.zero);
    if constexpr (I > 0 && I % 4 == 0) {
      wg_wait<0>(); pin<16>(&acc[0][64 - 16 * C]); pin<16>(&acc[1][64 - 16 * C]);
      SFOR(j, (I > 8 ? I - 2 : I - 1), I) pinr<8>(ff[j][0]); pinr<8>(ff[j][1]); });
    }
    wg_fence();
    SFOR(kk, 0, 2) SFOR(c, 0, 2)
      WgRS<128 - 32 * C, 0>::template run<doff(c * CV_ZS + (32 * C + M + kk) * 16, CV_ZC), dhi(128, 0), (I | kk) != 0>(
          acc[c], f[c][4 * kk], f[c][4 * kk + 1], f[c][4 * kk + 2], f[c][4 * kk + 3], X.dz);
    }); });
    wg_commit();
    if constexpr (C > 0 && I % 4 == 0) conv_send<C - 1>(acc, X);
    if constexpr (C > 0 && I % 4 == 1) conv_fetch<C - 1>(r, X);
    if constexpr (C > 0 && I % 4 == 2) conv_publish<C - 1>(acc, r, X);
    if constexpr (I % 4 >= D && I < 14) { wg_wait<D>(); pinr<8>(ff[I - D][0]); pinr<8>(ff[I - D][1]); }
    constexpr bool late = I < 4;
    if constexpr (I < 12 && I % 4 == (late ? 3 : 2)) mbar_wait(X.tb + 8 * (C + 1), 0);
    if constexpr (late && I % 4 == 3) conv_load<I + 1>(ff[I + 1], X.ta);
    if constexpr (I + 2 < 16 && !(late && I % 4 == 2)) conv_load<I + 2>(ff[I + 2], X.ta);
    if constexpr (I < 15) ConvStep<I + 1>::run(acc, ff, r, X);
    else {
      wg_wait<0>();
      pin<16>(acc[0]); pin<16>(acc[1]);
      SFOR(j, 12, 16) pinr<8>(ff[j][0]); pinr<8>(ff[j][1]); });
      conv_send<3>(acc, X); conv_fetch<3>(r, X); conv_publish<3>(acc, r, X);
    }
  }
};

__device__ __forceinline__ int pair_index(int p) {
  const int r7 = ((p - 36) * 37) >> 8;
  const int lo = ((p - 4) & 7) * 8 + ((p - 4) >> 3), hi = (p - 35 - 7 * r7) * 8 + 4 + r7;
  int r;
  asm("{.reg .pred a, b; setp.lt.s32 a, %1, 36; setp.lt.s32 b, %1, 4; selp.s32 %0, %2, %3, a; selp.s32 %0, %4, %0, b;}" : "=&r"(r) : "r"(p), "r"(lo), "r"(hi), "r"(4 + p));
  return r;
}

__global__ void __cluster_dims__(2, 1, 1) __launch_bounds__(384, 1)
fused_kernel(const __grid_constant__ Params P, const __grid_constant__ CUtensorMap tG1, const __grid_constant__ CUtensorMap tU1,
             const __grid_constant__ CUtensorMap tG2, const __grid_constant__ CUtensorMap tU2,
             const __grid_constant__ CUtensorMap tD64, const __grid_constant__ CUtensorMap tD48,
             const __grid_constant__ CUtensorMap tK, const __grid_constant__ CUtensorMap tV, const __grid_constant__ CUtensorMap tQ) {
  extern __shared__ __align__(1024) unsigned char smem_raw[];
  const uint32_t sb = (smem_u32(smem_raw) + 1023) & ~1023u;
  const uint32_t bars = sb + SM_BAR;
  const int tid = threadIdx.x, lane = tid & 31;
  const int wid = __reduce_max_sync(0xffffffffu, tid >> 5);
  const int wg = wid >> 2, warp = wid & 3;
  const int s = blockIdx.x & 1, pr = pair_index(blockIdx.x >> 1), bid = 2 * pr + s;
  const int tile = pr & 15, jn = pr >> 4;
  const int kb_own = 2 * jn + s, cf = 4 * s + jn;
#pragma unroll
  for (int i = 0; i < PERT; i++) lane_now();
  if (wg == 2) {
    asm volatile("setmaxnreg.dec.sync.aligned.u32 %0;" :: "n"(504 - 2 * CREG));
    auto kv_fetch = [&](int q) {
      tma3(sb + SM_W + q * 16384, &tK, bars + B_KV + 8 * q, pr * 8, q * 128 + s * 64 - 1, 0);
      tma3(sb + SM_W + q * 16384 + KV_V, &tV, bars + B_KV + 8 * q, pr * 8, q * 128 + s * 64 - 1, 0);
    };
    if (elect()) {
      if (warp == 0) {
#pragma unroll
        for (int i = 0; i < 7; i++) mbar_init(bars + 8 * i, 1);
        bulk_load(sb + SM_W + 4 * 16384, P.zk + (size_t)bid * 4 * SEQ, 8192, bars + B_Z);
        kv_fetch(0);
        bulk_load(sb + SM_W + 4 * 16384 + 8192, P.zk + (size_t)(bid * 4 + 2) * SEQ, 8192, bars + B_Z + 8);
#pragma unroll
        for (int i = 0; i < 7; i++) mbar_expect(bars + 8 * i, i < 4 ? 8320 : i < 6 ? 8192 : 16384);
      } else {
        const uint32_t b0 = bars + (warp == 1 ? B_PFULL : warp == 2 ? B_WEMPTY : B_VALID), cnt = warp == 2 ? 8 : 1;
        __nanosleep(100);
#pragma unroll
        for (int i = 0; i < 20; i++) mbar_init(b0 + 8 * i, cnt);
        if (warp != 2) {
#pragma unroll
          for (int i = 20; i < 42; i++) mbar_init(b0 + 8 * i, 1);
        } else {
#pragma unroll
          for (int i = 0; i < 4; i++) { mbar_init(bars + B_T + 8 * i, 5); mbar_expect(bars + B_T + 8 * i, 4096); }
#pragma unroll
          for (int i = 0; i < 8; i++) mbar_init(bars + B_YW + 8 * i, 1);
        }
      }
      asm volatile("fence.mbarrier_init.release.cluster;" ::: "memory");
    }
    __syncwarp();
    asm volatile("barrier.cluster.arrive.relaxed.aligned;" ::: "memory");
    const uint4 sk0 = __ldg(reinterpret_cast<const uint4*>(P.sk) + (pr * 2 + (lane & 1)) * 2), sk1 = __ldg(reinterpret_cast<const uint4*>(P.sk) + (pr * 2 + (lane & 1)) * 2 + 1);
    const uint32_t epoch = g_s.epoch[bid];
    asm volatile("barrier.cluster.wait.acquire.aligned;" ::: "memory");
    if (warp == 0) {
      for (const uint32_t t0 = clock(); (uint32_t)clock() - t0 < (uint32_t)Q1D;) {}
      if (elect()) kv_fetch(1);
      __syncwarp();
    }
    {
      const uint32_t w0[4] = {__byte_perm(sk0.x, sk0.z, 0x5410), __byte_perm(sk0.x, sk0.z, 0x7632), __byte_perm(sk0.y, sk0.w, 0x5410), __byte_perm(sk0.y, sk0.w, 0x7632)};
      const uint32_t w1[4] = {__byte_perm(sk1.x, sk1.z, 0x5410), __byte_perm(sk1.x, sk1.z, 0x7632), __byte_perm(sk1.y, sk1.w, 0x5410), __byte_perm(sk1.y, sk1.w, 0x7632)};
      const int m = (tid & 127) >> 1;
      const bool klocal = (lane & 1) == s;
      const uint32_t kcur = sb + SM_W + (m + 1) * 16 + (lane & 1) * 8, krbar = mapa(bars + B_T, lane & 1);
      uint32_t kdst = sb + SM_A + CV_T + (16 + s * 256 + m * 4) * 4;
      if (!klocal) kdst = mapa(kdst, lane & 1);
      const int g = lane & 7, t = lane >> 3;
      uint4* const yp = g_s.y + (8 * warp + 7 - 2 * t) * 1024 + bid * 8 + g;
#pragma unroll 1
      for (int it = 0; it < 4; it++) {
        mbar_wait(bars + B_KV + 8 * it, 0);
        if (it == 2 && warp == 0 && elect()) {
#pragma unroll
          for (int i = 0; i < 4; i++) tma2(sb + SM_W + 5 * 16384 + i * 4096, &tQ, bars + B_Q, kb_own * 64, i * 512 + tile * 32);
        }
        __syncwarp();
        kv_produce(kcur + it * 16384, kdst + it * 2048, klocal, krbar + 8 * it, w0, w1);
        __syncwarp();
        if (lane == 0) mbar_arrive(bars + B_T + 8 * it);
        if (it < 2 && warp == 0) {
          if (elect()) kv_fetch(it + 2);
          __syncwarp();
        }
        if (it == 2) {
#pragma unroll
          for (int i = 4; i < 8; i++) stg_ll128(yp + (i >> 1) * 32768 - (i & 1) * 1024, epoch, 0, 0, 0);
        }
        if (it >= WMIN) {
          if (it == WMIN) bar_sync(2, 384); else bar_sync(1, 128);
          if (warp == WW && elect()) {
#pragma unroll
            for (int g = 0; g < 5; g++) {
              const uint32_t full = bars + B_WFULL + 8 * g, dst = sb + SM_W + g * 16384;
              const int k0 = (kb_own ^ (g / 3)) << 6;
              if (it == ((WIT >> (4 * g)) & 15)) {
                if (g != 2) { mbar_expect(full, 12288); tma3(dst, &tG2, full, 0, k0 + 32 * (g % 3), 32 + 3 * cf); tma3(dst + 6144, &tU2, full, 0, k0 + 32 * (g % 3), 32 + 3 * cf); }
                else        { mbar_expect(full, 16384); tma3(dst, &tG1, full, 0, k0, 2 * cf); tma3(dst + 8192, &tU1, full, 0, k0, 2 * cf); }
              }
            }
          }
          __syncwarp();
        }
      }
    }
    bar_sync(1, 128);
    asm volatile("setmaxnreg.dec.sync.aligned.u32 %0;" :: "n"(504 - 2 * GREG));
    if (warp == 0) {
      if (elect()) {
        int st = 5, ph = 1;
#pragma unroll 1
        for (int it = 5; it < 96; it++) {
          if (it == 5 || it == 50) {
#pragma unroll
            for (int i = 0; i < 14; i++) mbar_expect(bars + B_AFULL + 8 * i, i % 7 ? 8192 : 4096);
            mbar_expect(bars + B_AF2, 4096); mbar_expect(bars + B_AF2 + 8, 4096);
          }
          const int g = it < 48 ? it : it - 48;
          const uint32_t full = bars + B_WFULL + 8 * st, dst = sb + SM_W + st * 16384;
          const CUtensorMap *m0, *m1;
          int k0, z0, z1;
          bool small;
          if (g < 32) {
            int n, r;
            if (g < 3 * NI) { n = (g * 43) >> 7; r = g - 3 * n; }
            else if (g < 16 + NI) { n = (g - NI) >> 1; r = (g - NI) & 1; }
            else if (g < 24) { n = g - 16; r = 2; }
            else { n = g - 24; r = 3; }
            small = r < 2;
            k0 = (((n < 2 ? kb_own : 2 * jn) ^ n) << 6) + (small ? 32 * r : 0);
            m0 = small ? &tG2 : &tG1; m1 = small ? &tU2 : &tU1;
            z0 = z1 = small ? 32 + 3 * cf : 2 * cf + r - 2;
          } else {
            const int e = g - 32;
            small = e < 9 && e != 2;
            const int x = small ? (e < 2 ? e : e - 1) : (e == 2 ? 0 : e - 8);
            k0 = small ? 1024 + 96 * (cf ^ (x >> 1)) + 48 * (x & 1) : 128 * (cf ^ (x & 3)) + 64 * (x >> 2);
            m0 = m1 = small ? &tD48 : &tD64;
            z0 = kb_own; z1 = kb_own ^ 1;
          }
          const uint32_t half = small ? 6144 : 8192;
          mbar_wait(bars + B_WEMPTY + 8 * st, ph ^ (st == 5));
          tma3(dst, m0, full, 0, k0, z0);
          tma3(dst + half, m1, full, 0, k0, z1);
          mbar_expect(full, 2 * half);
          if (it == 6 + (bid & 15)) l2_prefetch((const char*)P.wd + (size_t)bid * 14336, 14336);
          if (++st == 6) { st = 0; ph ^= 1; }
        }
      }
    } else if (warp == 1) {
#pragma unroll 1
      for (int layer = 0; layer < 2; layer++) {
#pragma unroll 1
        for (int i = 2; i < 6; i++) {
          const int w = i & 1, n = 2 + (i & 6) + s;
          const uint32_t full = bars + B_AFULL + w * 56 + 8 * (n - 1);
          mbar_wait(full - 16, layer);
          if (elect()) bulk_load_mc(sb + SM_A + w * 65536 + n * 8192, g_s.a + tile * 8192 + ((2 * jn) ^ n) * 1024 + w * 512, 8192, full);
          __syncwarp();
        }
#pragma unroll 1
        for (int q = 0; q < 12; q++) {
          if (q == 9 && layer == 0) {
            mbar_wait(bars + B_HEMPTY + 12 * 8, 0);
            if (elect()) {
              g_s.epoch[bid] = epoch + 1;
              mbar_expect(bars + B_Y, 16384);
#pragma unroll
              for (int i = 0; i < 8; i++) bulk_load(sb + SM_A + (i >> 2) * 65536 + O_Y + (i & 3) * 2048, g_s.y + ((i >> 1) * 32 + tile * 2 + (i & 1)) * 1024 + kb_own * 128, 2048, bars + B_Y);
            }
            __syncwarp();
          }
          mbar_wait(bars + B_HEMPTY + q * 8, layer);
          if (elect()) {
            const uint32_t bytes = q < 6 ? 6144 : 8192;
            const uint4* src = h_src(P, tile, cf, q);
            const uint32_t dst = sb + SM_A + h_off(q), full = bars + B_HFULL + q * 8;
            mbar_expect(full, 2 * bytes);
            bulk_load(dst, src, bytes, full);
            bulk_load(dst + 65536, src + 1792, bytes, full);
          }
          __syncwarp();
        }
      }
    } else {
      const int w = warp - 2;
      uint32_t rph = 0;
#pragma unroll 1
      for (int it = 0; it < 36; it++) {
        const int layer = it >= 18, i = it - 18 * layer, q = i - 6;
        if (i == 0) {
          const uint32_t sa = sb + SM_A + w * 65536;
          bar_sync(12 + w, 160);
          fence_async_smem();
          if (elect()) {
            const uint32_t t0 = clock();
            asm volatile("cp.async.bulk.global.shared::cta.bulk_group [%0], [%1], 8192;"
                         :: "l"(g_s.a + tile * 8192 + kb_own * 1024 + w * 512), "r"(sa) : "memory");
            asm volatile("cp.async.bulk.commit_group;" ::: "memory");
            asm volatile("cp.async.bulk.wait_group 0;" ::: "memory");
            auto to_partner = [&](int h) {
              asm volatile("cp.async.bulk.shared::cluster.shared::cta.mbarrier::complete_tx::bytes [%0], [%1], 4096, [%2];"
                           :: "r"(mapa(sa + 8192 + h * 4096, s ^ 1)), "r"(sa + h * 4096), "r"(mapa(bars + (h ? B_AF2 + 8 * w : B_AFULL + 56 * w), s ^ 1)) : "memory");
            };
            to_partner(0);
            while ((uint32_t)clock() - t0 < (layer ? AD1 : AD0)) __nanosleep(20);
            bulk_load_mc(sa + (2 + s) * 8192, g_s.a + tile * 8192 + ((2 * jn) ^ (2 + s)) * 1024 + w * 512, 8192, bars + B_AFULL + w * 56 + 8 * (1 + s));
            to_partner(1);
          }
          __syncwarp();
        }
        const uint32_t bytes = (i >= 6 && i < 12) ? 6144 : 8192;
        const uint32_t dst = sb + SM_A + w * 65536 + (i < 6 ? (i + 2) * 8192 : h_off(q));
        const uint32_t pa = dst + (lane >> 2) * 132 + (lane & 3) * 32;
        mbar_wait(i < 6 ? bars + B_AFULL + w * 56 + (i + 1) * 8 : bars + B_HFULL + q * 8, layer);
#pragma unroll 1
        for (int n = 0; n < SPIN_LIMIT; n++) {
          uint32_t v[8];
#pragma unroll
          for (int k = 0; k < 8; k++) v[k] = lds32(pa + ((k < 6 || bytes == 8192) ? k * 1024 : 0));
          const uint32_t all = v[0] & v[1] & v[2] & v[3] & v[4] & v[5] & v[6] & v[7], any = v[0] | v[1] | v[2] | v[3] | v[4] | v[5] | v[6] | v[7];
          if (__all_sync(0xffffffffu, ((layer ? ~any : all) & 1) != 0)) break;
          if (elect()) {
            mbar_expect(bars + B_RETRY + 8 * w, bytes);
            bulk_load(dst, i < 6 ? g_s.a + tile * 8192 + ((2 * jn) ^ (i + 2)) * 1024 + w * 512 : h_src(P, tile, cf, q) + w * 1792, bytes, bars + B_RETRY + 8 * w);
          }
          mbar_wait(bars + B_RETRY + 8 * w, rph);
          rph ^= 1;
        }
        if (lane == 0) mbar_arrive(bars + B_VALID + w * 144 + i * 8);
      }
    }
  } else {
    asm volatile("barrier.cluster.arrive.relaxed.aligned;" ::: "memory");
    asm volatile("prefetch.global.L1 [%0];" :: "l"(P.sk + pr * 32) : "memory");
    asm volatile("setmaxnreg.inc.sync.aligned.u32 %0;" :: "n"(CREG));
    const int g = lane >> 2, t = lane & 3;
    const uint32_t sa = sb + SM_A + wg * 65536;
    const int w8 = wg * 4 + warp;
    const int row0 = (w8 >> 1) * 512 + tile * 32 + (w8 & 1) * 16;
    const uint32_t ymask = (lane & 12) == 0;
    const uint32_t epoch = g_s.epoch[bid];
    const uint32_t dz0 = __ldg(reinterpret_cast<const uint32_t*>(P.dd) + bid * 2 + wg);
    {
      const int r = tid & 127;
      if (r < 32) sts128(sa + CV_Z + (r >> 4) * CV_ZS + ((r >> 3) & 1) * CV_ZC + (128 + (r & 7)) * 16, 0, 0, 0, 0);
      else if (r < 40) sts128(sa + CV_T + ((r >> 2) & 1) * CV_TS + (r & 3) * 16, 0, 0, 0, 0);
      asm volatile("barrier.cluster.wait.acquire.aligned;" ::: "memory");
      mbar_wait(bars + B_Z + 8 * wg, 0);
#pragma unroll
      for (int i = 0; i < 4; i++) {
        uint4 z = lds128(sb + SM_W + 4 * 16384 + wg * 8192 + i * 2048 + r * 16);
        if ((i & 1) == 0 && r == 0) z.x = pack2(blo(z.x) + (i ? bhi(dz0) : blo(dz0)), bhi(z.x));
        sts128(sa + CV_Z + (i >> 1) * CV_ZS + (r & 1) * CV_ZC + (127 - (r >> 1)) * 16 - (i & 1) * 1024, z.x, z.y, z.z, z.w);
      }
      fence_async_smem();
      bar_arrive(2, 384);
      stg_ll64(g_s.ma + tile * 2048 + w8 * 32 + lane + kb_own * 256, 0, 0);
    }
    bar_sync(3 + wg, 128);
    mbar_wait(bars + B_T, 0);
    {
      float acc[2][64];
      uint32_t f[16][2][8];
      ConvCtx X;
      X.ta = sa + CV_T + (16 - 8 + 128 * warp + g - 2 * t) * 4;
      X.dz = dlo(sa + CV_Z); X.tb = bars + B_T; X.id = (g >> 1) == t ? ((g & 1) ? 0x3F800000u : 0x3F80u) : 0u;
      X.rw = sa + CV_R + warp * 6144 + lane * 16;
      X.wg = wg; X.warp = warp; X.zero = __uint_as_float(P.zero ^ 0x80000000u);
#pragma unroll
      for (int v = 1; v < 4; v++) X.rr[v - 1] = sa + CV_R + ((warp - v) & 3) * 6144 + (v - 1 - (warp < v ? 3 : 0)) * 512 + lane * 16;
      X.yp = reinterpret_cast<uint2*>(g_s.y) + (8 * warp + 7 - 2 * t) * 2048 + (bid * 2 + wg) * 8 + g;
      X.yq = g_s.y + (8 * warp + 7 - g) * 1024 + (bid * 2 + wg) * 4 + t;
      X.ym = ymask; X.yn = ~lane & 1; X.yt = ~epoch;
      uint4 r[3];
      conv_load<0>(f[0], X.ta); conv_load<1>(f[1], X.ta);
      ConvStep<0>::run(acc, f, r, X);
    }
    const uint32_t ytag = ~epoch;
    auto yfetch = [&]() {
      if (elect()) { mbar_expect(bars + B_YW + 8 * w8, 2048); bulk_load(sa + 7 * 8192 + warp * 2048, g_s.y + row0 * 64 + kb_own * 128, 2048, bars + B_YW + 8 * w8); }
      __syncwarp();
    };
    yfetch();
    float x[32], y[32], sy[2];
    uint2 mv[8];
    uint2* mg = g_s.ma + tile * 2048 + w8 * 32 + lane;
    auto mom_load = [&]() {
#pragma unroll
      for (int i = 0; i < 8; i++) mv[i] = ldg_ll64(mg + i * 256);
    };
    {
      uint32_t xa[16], xq[16];
      mbar_wait(bars + B_Q, 0);
#pragma unroll
      for (int ks = 0; ks < 4; ks++) {
        const uint32_t qa = sb + SM_W + 5 * 16384 + (w8 * 16 + (lane & 7)) * 128;
        ldsm4(qa + (lane & 8) * 128 + (((2 * ks + (lane >> 4)) ^ (lane & 7)) << 4), xa[4 * ks], xa[4 * ks + 1], xa[4 * ks + 2], xa[4 * ks + 3]);
        ldsm4(qa + (lane & 16) * 64 + (((2 * ks + ((lane >> 3) & 1)) ^ (lane & 7)) << 4), xq[4 * ks], xq[4 * ks + 1], xq[4 * ks + 2], xq[4 * ks + 3]);
      }
      auto sums = [&](const uint32_t* m, float& dot, float& sum, float (&d0)[4]) {
        float d1[4] = {0.f, 0.f, 0.f, 0.f}, d2[4] = {0.f, 0.f, 0.f, 0.f};
#pragma unroll
        for (int ks = 0; ks < 4; ks++) {
          const uint32_t* a = m + 4 * ks;
          mma16816(d1, a[0], a[1], a[2], a[3], xq[4 * ks], xq[4 * ks + 1]);
          mma16816(d2, a[0], a[1], a[2], a[3], xq[4 * ks + 2], xq[4 * ks + 3]);
          mma16816(d0, a[0], a[1], a[2], a[3], 0x3F803F80u, 0x3F803F80u);
        }
        const float p1 = __shfl_sync(0xffffffffu, (g & 1) ? d1[1] : d1[0], 4 * g + (g >> 1));
        const float p2 = __shfl_sync(0xffffffffu, (g & 1) ? d2[3] : d2[2], 4 * g + (g >> 1));
        dot = (t & 2) ? p2 : p1; sum = (t & 2) ? d0[2] : d0[0];
      };
      float e[2], dx[4] = {0.f, 0.f, 0.f, 0.f};
      sums(xa, e[1], e[0], dx);
      pin<2>(e);
      uint2 yv[8];
#pragma unroll 1
      for (int n = 0; n < SPIN_LIMIT; n++) {
        mbar_wait(bars + B_YW + 8 * w8, n & 1);
        uint32_t bad = 0;
#pragma unroll
        for (int j = 0; j < 8; j++) { yv[j] = lds64(sa + 7 * 8192 + warp * 2048 + j * 256 + (t * 8 + g) * 8); bad |= yv[j].x ^ ytag; }
        if (__all_sync(0xffffffffu, (bad & ymask) == 0)) break;
        yfetch();
      }
      uint32_t ya[16];
#pragma unroll
      for (int j = 0; j < 8; j++) { ya[2 * j] = yv[j].x & ~ymask; ya[2 * j + 1] = yv[j].y; }
      float f[2], dy[4] = {0.f, 0.f, 0.f, 0.f};
      sums(ya, f[0], f[1], dy);
      stg_ll64(mg + kb_own * 256, __float_as_uint((t & 1) ? f[0] : e[0]) | 1, __float_as_uint((t & 1) ? f[1] : e[1]));
      mom_load();
      sy[0] = t ? 0.f : dy[0]; sy[1] = t ? 0.f : dy[2];
#pragma unroll
      for (int i = 0; i < 16; i++) { x[2 * i] = blo(xa[i]); x[2 * i + 1] = bhi(xa[i]); y[2 * i] = blo(ya[i]); y[2 * i + 1] = bhi(ya[i]); }
      bar_sync(3 + wg, 128);
      asm volatile("setmaxnreg.inc.sync.aligned.u32 %0;" :: "n"(GREG));
    }
    uint32_t tm[4];
#pragma unroll
    for (int i = 0; i < 4; i++) tm[i] = (lane & 7) == (warp & 1) * 4 + i;
#pragma unroll 1
    for (int layer = 0;; layer++) {
      const uint32_t tag = layer ^ 1;
      uint32_t xp[16];
      float mean[2];
      {
        float m4[4], m2[2];
#pragma unroll 1
        for (int n = 0; n < SPIN_LIMIT; n++) {
          uint32_t bad = 0;
#pragma unroll
          for (int i = 0; i < 8; i++) bad |= mv[i].x ^ tag;
          if (__all_sync(0xffffffffu, (bad & 1) == 0)) break;
#pragma unroll
          for (int i = 0; i < 8; i++) ldg_ll64_if(mv[i], mg + i * 256, (mv[i].x ^ tag) & 1);
        }
        if (lane == 0) mbar_arrive(bars + B_WEMPTY + 8 * 5);
#define F_(i, c) __uint_as_float(mv[i].c)
        m2[0] = ((F_(0, x) + F_(1, x)) + (F_(2, x) + F_(3, x))) + ((F_(4, x) + F_(5, x)) + (F_(6, x) + F_(7, x)));
        m2[1] = ((F_(0, y) + F_(1, y)) + (F_(2, y) + F_(3, y))) + ((F_(4, y) + F_(5, y)) + (F_(6, y) + F_(7, y)));
#undef F_
#pragma unroll
        for (int i = 0; i < 2; i++) {
          const float o = __shfl_xor_sync(0xffffffffu, m2[i], 1);
          m4[i] = (t & 1) ? o : m2[i]; m4[2 + i] = (t & 1) ? m2[i] : o;
        }
        const float inv = 1.f / DM;
        const float m = m4[0] * inv;
        const float r = rsqrtf(fmaxf(fmaf(-m, m, m4[1] * inv), 0.f) + 1e-5f);
        const float cf3[3] = {r, -m * r, fmaf(r * inv, fmaf(-m, m4[3], m4[2]), m)};
        float co[2][3];
#pragma unroll
        for (int i = 0; i < 3; i++) {
          const float o = __shfl_xor_sync(0xffffffffu, cf3[i], 2);
          co[0][i] = (t & 2) ? o : cf3[i]; co[1][i] = (t & 2) ? cf3[i] : o;
        }
        mean[0] = co[0][2]; mean[1] = co[1][2];
#pragma unroll
        for (int j = 0; j < 8; j++)
#pragma unroll
          for (int h = 0; h < 2; h++) {
            const float x0 = x[4 * j + 2 * h], x1 = x[4 * j + 2 * h + 1];
            xp[2 * j + h] = pack2(fmaf(fmaf(x0, co[h][0], co[h][1]), y[4 * j + 2 * h], x0 - co[h][2]),
                                  fmaf(fmaf(x1, co[h][0], co[h][1]), y[4 * j + 2 * h + 1], x1 - co[h][2]));
          }
#pragma unroll
        for (int ks = 0; ks < 4; ks++) stsm4(sa + ks * 2048 + warp * 512 + lane * 16, tagw(xp[4 * ks], tm[0], tag), tagw(xp[4 * ks + 2], tm[1], tag), tagw(xp[4 * ks + 1], tm[2], tag), tagw(xp[4 * ks + 3], tm[3], tag));
        bar_arrive(12 + wg, 160);
        pinr<16>(xp);
      }
      const uint32_t dA = dlo(sa), dB = dlo(sb + SM_W);
      uint32_t hh[56];
      uint32_t* hg = reinterpret_cast<uint32_t*>(g_s.h + ((tile * 8 + cf) * 2 + wg) * 1792) + warp * 128 + lane;
      {
        float a1[96], a2[64];
        float* const a3 = a1;
        float* const acc = a2;
        float rs[2] = {0.f, 0.f};
        uint2 vb[2];
        uint2* const vg = g_s.mb + (tile * 8 + w8) * 64;
        auto epi = [&](const float* a, int half, int j, int ks) {
          const int o = 4 * ks + (j & 1) * 2;
          hh[o]     = pack2(glu(a[4 * j], a[half + 4 * j], rs[0]), glu(a[4 * j + 1], a[half + 4 * j + 1], rs[0]));
          hh[o + 1] = pack2(glu(a[4 * j + 2], a[half + 4 * j + 2], rs[1]), glu(a[4 * j + 3], a[half + 4 * j + 3], rs[1]));
          if (j & 1) { hh[o] = tagw(hh[o], tm[1], tag); hh[o + 1] = tagw(hh[o + 1], tm[3], tag); }
          else       { hh[o] = tagw(hh[o], tm[0], tag); hh[o + 1] = tagw(hh[o + 1], tm[2], tag); }
          hg[ks * 512 + (j & 1) * 32] = hh[o]; hg[ks * 512 + (j & 1) * 32 + 64] = hh[o + 1];
        };
        SFOR(gs, 0, 48)
          constexpr int st = gs % 6, e = gs - 32;
          constexpr int n = gs < 3 * NI ? gs / 3 : gs < 16 + NI ? (gs - NI) / 2 : gs < 24 ? gs - 16 : gs - 24;
          constexpr int r = gs < 3 * NI ? gs % 3 : gs < 16 + NI ? (gs - NI) % 2 : gs < 24 ? 2 : 3;
          constexpr int E1 = 16 + NI;
          constexpr bool own = e == 0 || e == 1 || e == 2 || e == 12;
          constexpr int q = e < 12 ? e - 3 : e - 4;
          if constexpr (gs == LAGS) { if (wg == 1) bar_sync(15, 256); }
          mbar_wait(bars + B_WFULL + 8 * st, (gs / 6) & 1);
          if constexpr (gs == 3) mbar_wait(bars + B_AFULL + 56 * wg, layer);
          if constexpr (gs == 4) mbar_wait(bars + B_AF2 + 8 * wg, layer);
          if constexpr (gs < E1 && n >= 2 && r == 0) mbar_wait(bars + B_VALID + wg * 144 + (n - 2) * 8, layer);
          if constexpr (gs >= 32 && !own) mbar_wait(bars + B_VALID + wg * 144 + (q + 6) * 8, layer);
          wg_fence();
          if constexpr (gs < 2) {
            SFOR(kk, 0, 2)
              constexpr int o = 8 * gs + 4 * kk;
              WgRS<192, 1>::template run<doff(st * 16384 + kk * 1024, 2048), dhi(512, 2), (gs | kk) != 0>(a1, xp[o], xp[o + 1], xp[o + 2], xp[o + 3], dB);
            });
          } else if constexpr (gs == 2) {
            SFOR(kk, 0, 4)
              WgRS<128, 1>::template run<doff(st * 16384 + kk * 2048, 8192), dhi(1024, 1), kk != 0>(a2, xp[4 * kk], xp[4 * kk + 1], xp[4 * kk + 2], xp[4 * kk + 3], dB);
            });
          } else if constexpr (gs < 32 && r < 2) {
            SFOR(kk, 0, 2)
              WgSS<192, 1>::template run<doff(n * 8192 + (2 * r + kk) * 2048, 128), dhi(256, 0), doff(st * 16384 + kk * 1024, 2048), dhi(512, 2), (gs | kk) != 0>(a1, dA, dB);
            });
          } else if constexpr (gs < 32) {
            SFOR(kk, 0, 4)
              WgSS<128, 1>::template run<doff(n * 8192 + kk * 2048, 128), dhi(256, 0), doff(st * 16384 + kk * 2048, 8192), dhi(1024, 1), (n | kk) != 0>(r == 2 ? a2 : a3, dA, dB);
            });
          } else {
            constexpr int nk = (e < 9 && e != 2) ? 3 : 4;
            SFOR(kk, 0, nk)
              constexpr int ob = doff(st * 16384 + kk * 2048, nk * 2048);
              if constexpr (own) {
                constexpr int o = ((e == 12 ? 10 : 3 * e) + kk) * 4;
                WgRS<128, 1>::template run<ob, dhi(1024, 1), (e | kk) != 0>(acc, hh[o], hh[o + 1], hh[o + 2], hh[o + 3], dB);
              } else {
                WgSS<128, 1>::template run<doff(h_off(q) + kk * 2048, 128), dhi(256, 0), ob, dhi(1024, 1), 1>(acc, dA, dB);
              }
            });
          }
          wg_commit();
          if constexpr (gs == 47) { if (wg == 0) bar_arrive(15, 256); }
          if constexpr (gs == 5) {
            float v0 = 0.f, v1 = 0.f;
#pragma unroll
            for (int j = 0; j < 8; j++) {
              v0 = fmaf(blo(xp[2 * j]), blo(xp[2 * j]), fmaf(bhi(xp[2 * j]), bhi(xp[2 * j]), v0));
              v1 = fmaf(blo(xp[2 * j + 1]), blo(xp[2 * j + 1]), fmaf(bhi(xp[2 * j + 1]), bhi(xp[2 * j + 1]), v1));
            }
            v0 += __shfl_xor_sync(0xffffffffu, v0, 1); v1 += __shfl_xor_sync(0xffffffffu, v1, 1);
            v0 += __shfl_xor_sync(0xffffffffu, v0, 2); v1 += __shfl_xor_sync(0xffffffffu, v1, 2);
            if (t == 0) stg_ll64(vg + (lane_now() >> 2) + kb_own * 8, tagw(__float_as_uint(v0), 1, tag), __float_as_uint(v1));
          }
          auto vload = [&]() { const int l = lane_now(); const uint2* p = vg + (l >> 2) + (l & 3) * 16; vb[0] = ldg_ll64(p); vb[1] = ldg_ll64(p + 8); };
          if constexpr (gs == 12) vload();
          if constexpr (gs == 16) {
#pragma unroll 1
            for (int it = 0; it < SPIN_LIMIT; it++) {
              if (__all_sync(0xffffffffu, (((vb[0].x ^ tag) | (vb[1].x ^ tag)) & 1) == 0)) break;
              vload();
            }
            float v0 = __uint_as_float(vb[0].x) + __uint_as_float(vb[1].x), v1 = __uint_as_float(vb[0].y) + __uint_as_float(vb[1].y);
            v0 += __shfl_xor_sync(0xffffffffu, v0, 1); v1 += __shfl_xor_sync(0xffffffffu, v1, 1);
            v0 += __shfl_xor_sync(0xffffffffu, v0, 2); v1 += __shfl_xor_sync(0xffffffffu, v1, 2);
            rs[0] = 0.5f * rsqrtf(v0 * (1.f / DM) + 1e-5f); rs[1] = 0.5f * rsqrtf(v1 * (1.f / DM) + 1e-5f);
          }
          constexpr int ei = gs >= 32 ? gs - 32 : gs >= 24 ? gs - 24 : gs - E1;
          constexpr int j0 = gs < E1 ? 0 : gs >= 32 ? cut3(ei) : gs >= 24 ? cut2(ei) : cut1(ei);
          constexpr int j2 = gs < E1 ? 0 : gs >= 32 ? cut3(ei + 1) : gs >= 24 ? cut2(ei + 1) : cut1(ei + 1);
          constexpr int j1 = ei == 0 ? j0 : j2;
          auto slice = [&](int ja, int jb) {
#pragma unroll
            for (int j = ja; j < jb; j++) epi(gs >= 32 ? a3 : gs >= 24 ? a2 : a1, gs >= 24 ? 32 : 48, j, (gs >= 32 ? 10 : gs >= 24 ? 6 : 0) + (j >> 1));
          };
          slice(j0, j1);
          if constexpr (gs == 44) {
#pragma unroll
            for (int i = 0; i < 16; i++) { x[2 * i] = mean[i & 1] + blo(xp[i]); x[2 * i + 1] = mean[i & 1] + bhi(xp[i]); }
            pin<32>(x);
          }
          if constexpr (gs > 0) {
            wg_wait<1>();
            if (lane == 0) {
              mbar_arrive(bars + B_WEMPTY + 8 * ((gs + 5) % 6));
              SFOR(k, 0, 12) if constexpr (gs == h_go(k)) mbar_arrive(bars + B_HEMPTY + k * 8); });
              if constexpr (gs == 38) mbar_arrive(bars + B_HEMPTY + 12 * 8);
              if constexpr (gs == 42) {
                mbar_expect(bars + B_PFULL + 8 * w8, 2048);
                mbar_arrive_remote(mapa(bars + B_PREADY, s ^ 1));
              }
            }
          }
          if constexpr (gs == E1) pin<96>(a1);
          if constexpr (gs == 24 || gs == 32) pin<64>(gs == 24 ? a2 : a3);
          slice(j1, j2);
        });
        const int l = lane_now();
        const uint32_t pa = sa + O_PART + warp * 512 + l * 16;
        const uint32_t rpa = mapa(pa, s ^ 1), rbar = mapa(bars + B_PFULL + 8 * w8, s ^ 1);
        mbar_wait(bars + B_PREADY, layer);
        wg_wait<0>();
        pin<64>(acc); pinr<56>(hh);
#pragma unroll
        for (int ks = 0; ks < 4; ks++) {
          const float* a = acc + 32 + 8 * ks;
          asm volatile("st.async.weak.shared::cluster.mbarrier::complete_tx::bytes.v4.b32 [%0], {%1,%2,%3,%4}, [%5];"
                       :: "r"(rpa + ks * 2048), "r"(pack2(a[0], a[1])), "r"(pack2(a[2], a[3])), "r"(pack2(a[4], a[5])), "r"(pack2(a[6], a[7])), "r"(rbar) : "memory");
        }
#pragma unroll
        for (int i = 0; i < 32; i++) x[i] = fmaf(acc[i], rs[(i >> 1) & 1], x[i]);
        pin<32>(x);
        auto add_partner = [&]() {
          mbar_wait(bars + B_PFULL + 8 * w8, layer);
#pragma unroll
          for (int ks = 0; ks < 4; ks++) {
            const uint4 v = lds128(pa + ks * 2048);
            float* o = x + 8 * ks;
            o[0] = fmaf(blo(v.x), rs[0], o[0]); o[1] = fmaf(bhi(v.x), rs[0], o[1]); o[2] = fmaf(blo(v.y), rs[1], o[2]); o[3] = fmaf(bhi(v.y), rs[1], o[3]);
            o[4] = fmaf(blo(v.z), rs[0], o[4]); o[5] = fmaf(bhi(v.z), rs[0], o[5]); o[6] = fmaf(blo(v.w), rs[1], o[6]); o[7] = fmaf(bhi(v.w), rs[1], o[7]);
          }
        };
        if (layer == 1) { add_partner(); break; }
        mg = g_s.ma + tile * 2048 + w8 * 32 + l;
        const uint32_t keep = (l & 12) ? ~0u : ~1u;
        mbar_wait(bars + B_Y, 0);
#pragma unroll
        for (int j = 0; j < 8; j++) {
          const uint2 v = lds64(sa + O_Y + warp * 2048 + j * 256 + ((l & 3) * 8 + (l >> 2)) * 8);
          y[4 * j] = blo(v.x & keep); y[4 * j + 1] = bhi(v.x); y[4 * j + 2] = blo(v.y); y[4 * j + 3] = bhi(v.y);
        }
        pin<32>(y);
        add_partner();
      }
      float mo[2][4], m4[4], m2[2];
#pragma unroll
      for (int h = 0; h < 2; h++) {
        float u[2][3] = {{0.f, 0.f, 0.f}, {0.f, 0.f, 0.f}};
#pragma unroll
        for (int i = 0; i < 16; i++) {
          const int e = 4 * (i >> 1) + 2 * h + (i & 1);
          u[i & 1][0] += x[e]; u[i & 1][1] = fmaf(x[e], x[e], u[i & 1][1]); u[i & 1][2] = fmaf(x[e], y[e], u[i & 1][2]);
        }
#pragma unroll
        for (int i = 0; i < 3; i++) mo[h][i] = u[0][i] + u[1][i];
        mo[h][3] = sy[h];
      }
#pragma unroll
      for (int i = 0; i < 4; i++) m4[i] = ((t & 2) ? mo[1][i] : mo[0][i]) + __shfl_xor_sync(0xffffffffu, (t & 2) ? mo[0][i] : mo[1][i], 2);
#pragma unroll
      for (int i = 0; i < 2; i++) m2[i] = ((t & 1) ? m4[2 + i] : m4[i]) + __shfl_xor_sync(0xffffffffu, (t & 1) ? m4[i] : m4[2 + i], 1);
      stg_ll64(mg + kb_own * 256, __float_as_uint(m2[0]) & ~1u, __float_as_uint(m2[1]));
      mom_load();
    }
    {
      const uint32_t ob = sa + O_Y + warp * 2048;
      const int mr = (lane & 7) + (lane & 8), mc = lane >> 4;
#pragma unroll
      for (int ks = 0; ks < 4; ks++) {
        const float* a = x + 8 * ks;
        stsm4(ob + mr * 128 + (((2 * ks + mc) ^ (mr & 7)) << 4), pack2(a[0], a[1]), pack2(a[2], a[3]), pack2(a[4], a[5]), pack2(a[6], a[7]));
      }
      __syncwarp();
#pragma unroll
      for (int i = 0; i < 4; i++) {
        const int r = 4 * i + (lane >> 3), c = lane & 7;
        const uint4 v = lds128(ob + r * 128 + ((c ^ (r & 7)) << 4));
        asm volatile("st.global.v4.u32 [%0], {%1,%2,%3,%4};" :: "l"(P.out + (size_t)(row0 + r) * DM + kb_own * 64 + c * 8), "r"(v.x), "r"(v.y), "r"(v.z), "r"(v.w) : "memory");
      }
    }
  }
}

typedef CUresult (*EncodeFn)(CUtensorMap*, CUtensorMapDataType, cuuint32_t, void*, const cuuint64_t*, const cuuint64_t*,
                             const cuuint32_t*, const cuuint32_t*, CUtensorMapInterleave, CUtensorMapSwizzle,
                             CUtensorMapL2promotion, CUtensorMapFloatOOBfill);

}

extern "C" void kernel_launch(void* const* d_in, const int* in_sizes, int n_in, void* d_out, int out_size) {
  static EncodeFn enc = nullptr;
  static Scratch* scratch = nullptr;
  if (!enc) {
    void* fn = nullptr; cudaDriverEntryPointQueryResult qr;
    cudaGetDriverEntryPoint("cuTensorMapEncodeTiled", &fn, cudaEnableDefault, &qr);
    enc = (EncodeFn)fn;
    cudaGetSymbolAddress((void**)&scratch, g_scratch);
    cudaFuncSetAttribute(fused_kernel, cudaFuncAttributeMaxDynamicSharedMemorySize, SM_TOTAL);
  }
  Params P;
  P.q = (const __nv_bfloat16*)d_in[0]; P.k = (const __nv_bfloat16*)d_in[1]; P.v = (const __nv_bfloat16*)d_in[2];
  P.sk = (const __nv_bfloat16*)d_in[3]; P.zk = (const __nv_bfloat16*)d_in[4]; P.dd = (const __nv_bfloat16*)d_in[5];
  P.wg = (const __nv_bfloat16*)d_in[7]; P.wu = (const __nv_bfloat16*)d_in[8]; P.wd = (const __nv_bfloat16*)d_in[9];
  P.out = (__nv_bfloat16*)d_out; P.zero = 0; P.gs = scratch;
  CUtensorMap tG1, tU1, tG2, tU2, tD64, tD48, tK, tV, tQ;
  const cuuint32_t es[3] = {1, 1, 1};
  {
    const cuuint64_t gd[3] = {64, DM, FF / 64}, gs[2] = {FF * 2, 128}; const cuuint32_t bx[3] = {64, 64, 1};
    enc(&tG1, CU_TENSOR_MAP_DATA_TYPE_BFLOAT16, 3, (void*)P.wg, gd, gs, bx, es, CU_TENSOR_MAP_INTERLEAVE_NONE, CU_TENSOR_MAP_SWIZZLE_128B, CU_TENSOR_MAP_L2_PROMOTION_L2_128B, CU_TENSOR_MAP_FLOAT_OOB_FILL_NONE);
    enc(&tU1, CU_TENSOR_MAP_DATA_TYPE_BFLOAT16, 3, (void*)P.wu, gd, gs, bx, es, CU_TENSOR_MAP_INTERLEAVE_NONE, CU_TENSOR_MAP_SWIZZLE_128B, CU_TENSOR_MAP_L2_PROMOTION_L2_128B, CU_TENSOR_MAP_FLOAT_OOB_FILL_NONE);
  }
  {
    const cuuint64_t gd[3] = {32, DM, FF / 32}, gs[2] = {FF * 2, 64}; const cuuint32_t bx[3] = {32, 32, 3};
    enc(&tG2, CU_TENSOR_MAP_DATA_TYPE_BFLOAT16, 3, (void*)P.wg, gd, gs, bx, es, CU_TENSOR_MAP_INTERLEAVE_NONE, CU_TENSOR_MAP_SWIZZLE_64B, CU_TENSOR_MAP_L2_PROMOTION_L2_128B, CU_TENSOR_MAP_FLOAT_OOB_FILL_NONE);
    enc(&tU2, CU_TENSOR_MAP_DATA_TYPE_BFLOAT16, 3, (void*)P.wu, gd, gs, bx, es, CU_TENSOR_MAP_INTERLEAVE_NONE, CU_TENSOR_MAP_SWIZZLE_64B, CU_TENSOR_MAP_L2_PROMOTION_L2_128B, CU_TENSOR_MAP_FLOAT_OOB_FILL_NONE);
  }
  {
    const cuuint64_t gd[3] = {64, FF, DM / 64}, gs[2] = {DM * 2, 128}; const cuuint32_t b64[3] = {64, 64, 1}, b48[3] = {64, 48, 1};
    enc(&tD64, CU_TENSOR_MAP_DATA_TYPE_BFLOAT16, 3, (void*)P.wd, gd, gs, b64, es, CU_TENSOR_MAP_INTERLEAVE_NONE, CU_TENSOR_MAP_SWIZZLE_128B, CU_TENSOR_MAP_L2_PROMOTION_L2_128B, CU_TENSOR_MAP_FLOAT_OOB_FILL_NONE);
    enc(&tD48, CU_TENSOR_MAP_DATA_TYPE_BFLOAT16, 3, (void*)P.wd, gd, gs, b48, es, CU_TENSOR_MAP_INTERLEAVE_NONE, CU_TENSOR_MAP_SWIZZLE_128B, CU_TENSOR_MAP_L2_PROMOTION_L2_128B, CU_TENSOR_MAP_FLOAT_OOB_FILL_NONE);
  }
  {
    const cuuint64_t gd[3] = {DM, SEQ / 4, 4}, gs[2] = {DM * 2 * 4, DM * 2}; const cuuint32_t bx[3] = {8, 65, 4};
    enc(&tK, CU_TENSOR_MAP_DATA_TYPE_BFLOAT16, 3, (void*)P.k, gd, gs, bx, es, CU_TENSOR_MAP_INTERLEAVE_NONE, CU_TENSOR_MAP_SWIZZLE_NONE, CU_TENSOR_MAP_L2_PROMOTION_L2_128B, CU_TENSOR_MAP_FLOAT_OOB_FILL_NONE);
    enc(&tV, CU_TENSOR_MAP_DATA_TYPE_BFLOAT16, 3, (void*)P.v, gd, gs, bx, es, CU_TENSOR_MAP_INTERLEAVE_NONE, CU_TENSOR_MAP_SWIZZLE_NONE, CU_TENSOR_MAP_L2_PROMOTION_L2_128B, CU_TENSOR_MAP_FLOAT_OOB_FILL_NONE);
    const cuuint64_t qd[2] = {DM, SEQ}, qs[1] = {DM * 2}; const cuuint32_t qb[2] = {64, 32};
    enc(&tQ, CU_TENSOR_MAP_DATA_TYPE_BFLOAT16, 2, (void*)P.q, qd, qs, qb, es, CU_TENSOR_MAP_INTERLEAVE_NONE, CU_TENSOR_MAP_SWIZZLE_128B, CU_TENSOR_MAP_L2_PROMOTION_L2_128B, CU_TENSOR_MAP_FLOAT_OOB_FILL_NONE);
  }
  fused_kernel<<<NCTA, 384, SM_TOTAL, cudaStreamPerThread>>>(P, tG1, tU1, tG2, tU2, tD64, tD48, tK, tV, tQ);
}
```
